```python
import torch

def _softmax(x, axis=-1):
    return torch.softmax(x, dim=axis)
def _gelu(x):
    return torch.nn.functional.gelu(x, approximate="tanh")
def _silu(x):
    return torch.nn.functional.silu(x)
def _sigmoid(x):
    return torch.sigmoid(x)
def _layernorm(x, axis=-1, eps=1e-5):
    m = x.mean(dim=axis, keepdim=True)
    v = x.var(dim=axis, keepdim=True, unbiased=False)
    return (x - m) / torch.sqrt(v + eps)
def _scatter_add(tgt, idx, src, axis=0):
    return tgt.clone().index_add_(axis, idx, src)
def _segment_sum(src, seg, n):
    out = torch.zeros((n,) + src.shape[1:], dtype=src.dtype)
    return out.index_add_(0, seg, src)
def _pad(x, pw):
    flat = tuple(v for pair in reversed(pw) for v in pair)
    return torch.nn.functional.pad(x, flat)

kernel_name = 'parallel_sum__ssm_conv_s4__mixer_channel_mlp__prompt'

def setup_inputs():

    _w = (lambda a: (lambda t: t.to(torch.bfloat16) if t.is_floating_point() else t)(torch.as_tensor(a)))
    def _A_setup():
        B, L, D, N = 1, 2048, 640, 128
        A_re = -(lambda _x: torch.exp(torch.as_tensor(_x)))((lambda *s: torch.randn(*s, dtype=torch.bfloat16) * 3.2)(D, N))
        A_im = torch.pi * (lambda *s: torch.randn(*s, dtype=torch.bfloat16) * 0.05)(D, N)
        B_re = (lambda *s: torch.randn(*s, dtype=torch.bfloat16) * 0.1)(D, N)
        B_im = (lambda *s: torch.randn(*s, dtype=torch.bfloat16) * 0.1)(D, N)
        C_re = (lambda *s: torch.randn(*s, dtype=torch.bfloat16) * 0.1)(D, N)
        C_im = (lambda *s: torch.randn(*s, dtype=torch.bfloat16) * 0.1)(D, N)
        log_dt = (lambda *s: torch.randn(*s, dtype=torch.bfloat16) * 0.05)(D) * 0.5 - 4.0
        Dskip = (lambda *s: torch.randn(*s, dtype=torch.bfloat16) * 0.05)(D)
        return {
            "u": _w((lambda *s: torch.randn(*s, dtype=torch.bfloat16) * 0.05)(B, L, D)),
            "A_re": _w(A_re),
            "A_im": _w(A_im),
            "B_re": _w(B_re),
            "B_im": _w(B_im),
            "C_re": _w(C_re),
            "C_im": _w(C_im),
            "log_dt": _w(log_dt),
            "Dskip": _w(Dskip),
        }
    _A_in = _A_setup()

    def _B_setup():
        B, S, D, F = 1, 2048, 640, 1728
        return {
            "x": _w((lambda *s: torch.randn(*s, dtype=torch.bfloat16) * 0.05)(B, S, D)),
            "w1": _w((lambda *s: torch.randn(*s, dtype=torch.bfloat16) * 1.6)(D, F) * (D ** -0.5)),
            "b1": _w((lambda *s: torch.randn(*s, dtype=torch.bfloat16) * 0.8)(F)),
            "w2": _w((lambda *s: torch.randn(*s, dtype=torch.bfloat16) * 0.05)(F, D) * (F ** -0.5)),
            "b2": _w((lambda *s: torch.randn(*s, dtype=torch.bfloat16) * 0.05)(D)),
        }
    _B_in = _B_setup()

    return {
        "A_u": _A_in["u"],
        "A_A_re": _A_in["A_re"],
        "A_A_im": _A_in["A_im"],
        "A_B_re": _A_in["B_re"],
        "A_B_im": _A_in["B_im"],
        "A_C_re": _A_in["C_re"],
        "A_C_im": _A_in["C_im"],
        "A_log_dt": _A_in["log_dt"],
        "A_Dskip": _A_in["Dskip"],
        "B_x": _B_in["x"],
        "B_w1": _B_in["w1"],
        "B_b1": _B_in["b1"],
        "B_w2": _B_in["w2"],
        "B_b2": _B_in["b2"],
    }

def reference(A_u, A_A_re, A_A_im, A_B_re, A_B_im, A_C_re, A_C_im, A_log_dt, A_Dskip, B_x, B_w1, B_b1, B_w2, B_b2):
    def _A_ref(u, A_re, A_im, B_re, B_im, C_re, C_im, log_dt, Dskip):
        Bsz, L, D = u.shape
        dt = torch.exp(log_dt)[:, None]
        A = A_re + 1j * A_im
        Bc = B_re + 1j * B_im
        Cc = C_re + 1j * C_im
        logdA = dt * A
        dB = dt * Bc
        l = (lambda x, dt: x.to(dt))(torch.arange(L), A_re.dtype)
        P = torch.exp(logdA[:, :, None] * l[None, None, :])
        K = torch.einsum("dn,dnl,dn->dl", Cc, P, dB).real
        L2 = 2 * L
        Kp = _pad(K, ((0, 0), (0, L)))
        up = (lambda x, *d: x.permute(*d))(u, 0, 2, 1)
        up = _pad(up, ((0, 0), (0, 0), (0, L)))
        Kf = (lambda x, axes=(-2,-1): torch.fft.rfft2(x.float(), dim=axes))(Kp[:, None, :], axes=(-2, -1))
        Uf = (lambda x, axes=(-2,-1): torch.fft.rfft2(x.float(), dim=axes))(up[:, :, None, :], axes=(-2, -1))
        Yf = Uf * Kf[None, :, :, :]
        y = (lambda x, s, axes=(-2,-1): torch.fft.irfft2(x, s=s, dim=axes).to(torch.bfloat16))(Yf, (1, L2), axes=(-2, -1))[:, :, 0, :L]
        y = (lambda x, *d: x.permute(*d))(y, 0, 2, 1) + u * Dskip[None, None, :]
        return y

    def _B_ref(x, w1, b1, w2, b2):
        y = _layernorm(x, axis=-1)
        h = _gelu(torch.einsum("bsd,df->bsf", y, w1) + b1)
        return torch.einsum("bsf,fd->bsd", h, w2) + b2

    x = A_u
    xn = _layernorm(x, axis=-1)
    return x + _A_ref(xn, A_A_re, A_A_im, A_B_re, A_B_im, A_C_re, A_C_im, A_log_dt, A_Dskip) + _B_ref(xn, B_w1, B_b1, B_w2, B_b2)
```

```cpp
#include <cuda_runtime.h>
#include <cuda_bf16.h>
#include <cuda.h>
#include <stdint.h>

#define ABL 0

namespace {

constexpr int SEQ = 2048, DM = 640, FF = 1728, NMODE = 128;
constexpr int NMLP = 96;

constexpr uint32_t CW = 50176;
constexpr uint32_t C_U = 1024, C_Y1 = 10240, C_Y2 = 18432, C_Y3 = 21504;
constexpr uint32_t C_X5 = 23552, C_X3 = C_X5 + 6912, C_X7 = C_X3 + 6912, C_X9 = C_X7 + 2048;
constexpr uint32_t C_KA = C_Y1, C_KB = C_Y1 + 16640;
constexpr uint32_t C_T = C_X9 + 2048, TCP = 2112, TCH = 2 * TCP;
constexpr uint32_t C_S = 4 * CW;
constexpr int T_B0 = 32, T_B1 = 336, T_F7 = 640, T_F9 = 736, T_C5 = 864, T_C3 = 992;
constexpr int NPC = 224;
constexpr uint32_t SLOT = 20480;
constexpr int NSLOT = 5;
constexpr uint32_t ZONE = NSLOT * SLOT, ZSZ = 36864;
constexpr uint32_t XR0 = ZONE, XR1 = ZONE + 49152, LNS = ZONE + 24576;
constexpr uint32_t MCW = ZONE + 2 * ZSZ;
constexpr uint32_t TCS = MCW + CW;
constexpr uint32_t STATS = TCS + 2304;
constexpr uint32_t BARS = 229888, MISC = BARS + 384;
constexpr uint32_t SMEM_BYTES = BARS + 2048;
constexpr int B_FULL = 0, B_XF = 5, B_HIN = 11, B_YT = 13, B_XE = 14, B_HRDY = 20, B_CS = 22, B_LI = 23, B_CV = 24,
              B_EMPTY = 28,
              B_LN = 33, B_HFREE = 34, B_TAB = 35, B_OUT = 36, B_YT2 = 37, NBAR = 38, B_LI2 = 38;
constexpr int B_GO = 16, B_SP = 17;

constexpr uint32_t HI_SW128 = (1024u >> 4) | (1u << 30);
constexpr uint32_t HI_SW64 = (512u >> 4) | (2u << 30);
constexpr uint32_t HI_SW32 = (256u >> 4) | (3u << 30);
constexpr uint32_t HI_XI = (2304u >> 4);
constexpr uint32_t HI_KG = (128u >> 4);

struct Scratch {
  __nv_bfloat16 xnT[DM * SEQ], yT[DM * SEQ];
  float2 stats[SEQ];
  float csp[2][FF];
  unsigned cnt1, pad1[31], cnt2, pad2[31], cnt3, pad3[31], ycnt[10 * 32], epoch[132 * 4];
};
__device__ __align__(1024) Scratch g_s;
#define PROF(slot) do {} while (0)
#define PROFC(cond, slot) do {} while (0)
#define PROFDUMP() do {} while (0)

struct Params {
  const __nv_bfloat16 *x, *Are, *Aim, *Bre, *Bim, *Cre, *Cim, *logdt, *dskip, *w1, *b1, *w2, *b2;
  Scratch* S;
};
struct Maps { CUtensorMap X, W1, W1h, W2, W22, Y, O, Xl, Ol, U, Yr; };

__device__ __forceinline__ uint32_t smem_u32(const void* p) { return (uint32_t)__cvta_generic_to_shared(p); }
__device__ __forceinline__ void mbar_init(uint32_t bar, int cnt) { asm volatile("mbarrier.init.shared::cta.b64 [%0], %1;" ::"r"(bar), "r"(cnt)); }
__device__ __forceinline__ void mbar_expect(uint32_t bar, uint32_t bytes) { asm volatile("mbarrier.arrive.expect_tx.shared::cta.b64 _, [%0], %1;" ::"r"(bar), "r"(bytes) : "memory"); }
__device__ __forceinline__ void mbar_arrive(uint32_t bar) { asm volatile("mbarrier.arrive.shared::cta.b64 _, [%0];" ::"r"(bar) : "memory"); }
__device__ __forceinline__ void mbar_arrive_cluster(uint32_t rbar) { asm volatile("mbarrier.arrive.relaxed.cluster.shared::cluster.b64 _, [%0];" ::"r"(rbar) : "memory"); }
__device__ __forceinline__ void mbar_wait(uint32_t bar, uint32_t parity) {
  asm volatile("{\n.reg .pred p;\n.reg .b32 i;\nmov.b32 i, 0;\nW_%=:\nmbarrier.try_wait.parity.shared::cta.b64 p, [%0], %1;\n@p bra D_%=;\n"
               "add.u32 i, i, 1;\nsetp.lt.u32 p, i, 0x1000000;\n@p bra W_%=;\ntrap;\nD_%=:\n}" ::"r"(bar), "r"(parity) : "memory");
}
__device__ __forceinline__ void mbar_wait_cluster(uint32_t bar, uint32_t parity) {
  asm volatile("{\n.reg .pred p;\n.reg .b32 i;\nmov.b32 i, 0;\nW_%=:\nmbarrier.try_wait.parity.acquire.cluster.shared::cta.b64 p, [%0], %1;\n@p bra D_%=;\n"
               "add.u32 i, i, 1;\nsetp.lt.u32 p, i, 0x1000000;\n@p bra W_%=;\ntrap;\nD_%=:\n}" ::"r"(bar), "r"(parity) : "memory");
}
__device__ __forceinline__ void poll_ge(const unsigned* ptr, unsigned target) {
  asm volatile("{\n.reg .pred p;\n.reg .b32 i, v;\nmov.b32 i, 0;\nW_%=:\nld.acquire.gpu.global.u32 v, [%0];\nsub.s32 v, v, %1;\nsetp.ge.s32 p, v, 0;\n@p bra D_%=;\n"
               "add.u32 i, i, 1;\nsetp.lt.u32 p, i, 0x400000;\n@p bra W_%=;\ntrap;\nD_%=:\n}" ::"l"(ptr), "r"(target) : "memory");
}
__device__ __forceinline__ uint32_t mapa(uint32_t a, uint32_t rank) { uint32_t r; asm volatile("mapa.shared::cluster.u32 %0, %1, %2;" : "=r"(r) : "r"(a), "r"(rank)); return r; }
__device__ __forceinline__ void tma2d(uint32_t dst, const CUtensorMap* tm, int c0, int c1, uint32_t bar) {
  asm volatile("cp.async.bulk.tensor.2d.shared::cluster.global.mbarrier::complete_tx::bytes [%0], [%1, {%3, %4}], [%2];"
               ::"r"(dst), "l"(tm), "r"(bar), "r"(c0), "r"(c1) : "memory");
}
__device__ __forceinline__ void tma2d_store(const CUtensorMap* tm, uint32_t src, int c0, int c1) {
  asm volatile("cp.async.bulk.tensor.2d.global.shared::cta.bulk_group [%0, {%2, %3}], [%1];" ::"l"(tm), "r"(src), "r"(c0), "r"(c1) : "memory");
}
__device__ __forceinline__ void bar_sync(int id, int n) { asm volatile("bar.sync %0, %1;" ::"r"(id), "r"(n) : "memory"); }
__device__ __forceinline__ void bar_arrive(int id, int n) { asm volatile("bar.arrive %0, %1;" ::"r"(id), "r"(n) : "memory"); }
__device__ __forceinline__ void fence_async_smem() { asm volatile("fence.proxy.async.shared::cta;" ::: "memory"); }
#define WG_FENCE() asm volatile("wgmma.fence.sync.aligned;" ::: "memory")
#define WG_COMMIT() asm volatile("wgmma.commit_group.sync.aligned;" ::: "memory")
#define WG_WAIT(n) asm volatile("wgmma.wait_group.sync.aligned %0;" ::"n"(n) : "memory")
__device__ __forceinline__ uint32_t pack_bf16(float lo, float hi) { uint32_t r; asm("cvt.rn.bf16x2.f32 %0, %1, %2;" : "=r"(r) : "f"(hi), "f"(lo)); return r; }
__device__ __forceinline__ float bf_lo(uint32_t w) { return __uint_as_float(w << 16); }
__device__ __forceinline__ float bf_hi(uint32_t w) { return __uint_as_float(w & 0xffff0000u); }
__device__ __forceinline__ float bf_round(float v) { return __uint_as_float(pack_bf16(0.f, v) & 0xffff0000u); }
__device__ __forceinline__ float ld_bf(const __nv_bfloat16* p) { return __uint_as_float((uint32_t)__ldg((const unsigned short*)p) << 16); }
__device__ __forceinline__ uint32_t hadd2(uint32_t a, uint32_t b) { uint32_t r; asm("add.rn.bf16x2 %0, %1, %2;" : "=r"(r) : "r"(a), "r"(b)); return r; }
__device__ __forceinline__ uint32_t lds32(uint32_t a) { uint32_t v; asm volatile("ld.shared.u32 %0, [%1];" : "=r"(v) : "r"(a) : "memory"); return v; }
__device__ __forceinline__ uint4 lds128(uint32_t a) { uint4 v; asm volatile("ld.shared.v4.u32 {%0,%1,%2,%3}, [%4];" : "=r"(v.x), "=r"(v.y), "=r"(v.z), "=r"(v.w) : "r"(a) : "memory"); return v; }
__device__ __forceinline__ void sts16(uint32_t a, uint32_t v) { asm volatile("st.shared.u16 [%0], %1;" ::"r"(a), "h"((unsigned short)v) : "memory"); }
__device__ __forceinline__ void sts32(uint32_t a, uint32_t v) { asm volatile("st.shared.u32 [%0], %1;" ::"r"(a), "r"(v) : "memory"); }
__device__ __forceinline__ void sts64(uint32_t a, uint32_t x, uint32_t y) { asm volatile("st.shared.v2.u32 [%0], {%1,%2};" ::"r"(a), "r"(x), "r"(y) : "memory"); }
__device__ __forceinline__ void sts128(uint32_t a, uint32_t x, uint32_t y, uint32_t z, uint32_t w) { asm volatile("st.shared.v4.u32 [%0], {%1,%2,%3,%4};" ::"r"(a), "r"(x), "r"(y), "r"(z), "r"(w) : "memory"); }
__device__ __forceinline__ void ldsm4(uint32_t (&r)[4], uint32_t a) { asm volatile("ldmatrix.sync.aligned.m8n8.x4.shared.b16 {%0,%1,%2,%3}, [%4];" : "=r"(r[0]), "=r"(r[1]), "=r"(r[2]), "=r"(r[3]) : "r"(a) : "memory"); }
__device__ __forceinline__ void ldsm4t(uint32_t (&r)[4], uint32_t a) { asm volatile("ldmatrix.sync.aligned.m8n8.x4.trans.shared.b16 {%0,%1,%2,%3}, [%4];" : "=r"(r[0]), "=r"(r[1]), "=r"(r[2]), "=r"(r[3]) : "r"(a) : "memory"); }
__device__ __forceinline__ void stsm4(uint32_t a, uint32_t r0, uint32_t r1, uint32_t r2, uint32_t r3) { asm volatile("stmatrix.sync.aligned.m8n8.x4.shared.b16 [%0], {%1,%2,%3,%4};" ::"r"(a), "r"(r0), "r"(r1), "r"(r2), "r"(r3) : "memory"); }
__device__ __forceinline__ void stsm4t(uint32_t a, uint32_t r0, uint32_t r1, uint32_t r2, uint32_t r3) { asm volatile("stmatrix.sync.aligned.m8n8.x4.trans.shared.b16 [%0], {%1,%2,%3,%4};" ::"r"(a), "r"(r0), "r"(r1), "r"(r2), "r"(r3) : "memory"); }
__device__ __forceinline__ uint32_t lds32n(uint32_t a) { uint32_t v; asm("ld.shared.u32 %0, [%1];" : "=r"(v) : "r"(a)); return v; }
__device__ __forceinline__ uint4 lds128n(uint32_t a) { uint4 v; asm("ld.shared.v4.u32 {%0,%1,%2,%3}, [%4];" : "=r"(v.x), "=r"(v.y), "=r"(v.z), "=r"(v.w) : "r"(a)); return v; }
__device__ __forceinline__ uint32_t hfma2(uint32_t a, uint32_t b, uint32_t c) { uint32_t r; asm("fma.rn.bf16x2 %0, %1, %2, %3;" : "=r"(r) : "r"(a), "r"(b), "r"(c)); return r; }
__device__ __forceinline__ uint32_t hmul2(uint32_t a, uint32_t b) { uint32_t r; asm("mul.rn.bf16x2 %0, %1, %2;" : "=r"(r) : "r"(a), "r"(b)); return r; }
__device__ __forceinline__ float sqrt_fast(float x) { float r; asm("sqrt.approx.f32 %0, %1;" : "=f"(r) : "f"(x)); return r; }
__device__ __forceinline__ float rcp_fast(float x) { float r; asm("rcp.approx.f32 %0, %1;" : "=f"(r) : "f"(x)); return r; }
__device__ __forceinline__ uint32_t sw128(uint32_t a) { return a ^ (((a >> 7) & 7u) << 4); }
__device__ __forceinline__ uint32_t sw64(uint32_t a) { return a ^ ((a >> 3) & 48u); }
__device__ __forceinline__ uint32_t sw32(uint32_t a) { return a ^ ((a >> 3) & 16u); }
__device__ __forceinline__ float ex2f(float x) { float r; asm("ex2.approx.ftz.f32 %0, %1;" : "=f"(r) : "f"(x)); return r; }
__device__ __forceinline__ float tanhf_fast(float x) { float r; asm("tanh.approx.f32 %0, %1;" : "=f"(r) : "f"(x)); return r; }
__device__ __forceinline__ uint2 ldcg64(const void* p) { uint2 v; asm volatile("ld.global.cg.v2.u32 {%0,%1}, [%2];" : "=r"(v.x), "=r"(v.y) : "l"(p) : "memory"); return v; }

__device__ __forceinline__ void wg_ss96(float (&d)[48], uint32_t alo, uint32_t ahi, uint32_t blo, uint32_t bhi, int sd) {
  asm volatile("{\n.reg .pred p;\n.reg .b64 da, db;\nsetp.ne.b32 p, %52, 0;\nmov.b64 da, {%48, %49};\nmov.b64 db, {%50, %51};\n"
    "wgmma.mma_async.sync.aligned.m64n96k16.f32.bf16.bf16 {%0,%1,%2,%3,%4,%5,%6,%7,%8,%9,%10,%11,%12,%13,%14,%15,%16,%17,%18,%19,%20,%21,%22,%23,%24,%25,%26,%27,%28,%29,%30,%31,%32,%33,%34,%35,%36,%37,%38,%39,%40,%41,%42,%43,%44,%45,%46,%47}, da, db, p, 1, 1, 0, 1;\n}\n"
    : "+f"(d[0]),"+f"(d[1]),"+f"(d[2]),"+f"(d[3]),"+f"(d[4]),"+f"(d[5]),"+f"(d[6]),"+f"(d[7]),"+f"(d[8]),"+f"(d[9]),"+f"(d[10]),"+f"(d[11]),"+f"(d[12]),"+f"(d[13]),"+f"(d[14]),"+f"(d[15]),"+f"(d[16]),"+f"(d[17]),"+f"(d[18]),"+f"(d[19]),"+f"(d[20]),"+f"(d[21]),"+f"(d[22]),"+f"(d[23]),"+f"(d[24]),"+f"(d[25]),"+f"(d[26]),"+f"(d[27]),"+f"(d[28]),"+f"(d[29]),"+f"(d[30]),"+f"(d[31]),"+f"(d[32]),"+f"(d[33]),"+f"(d[34]),"+f"(d[35]),"+f"(d[36]),"+f"(d[37]),"+f"(d[38]),"+f"(d[39]),"+f"(d[40]),"+f"(d[41]),"+f"(d[42]),"+f"(d[43]),"+f"(d[44]),"+f"(d[45]),"+f"(d[46]),"+f"(d[47])
    : "r"(alo), "r"(ahi), "r"(blo), "r"(bhi), "r"(sd));
}
__device__ __forceinline__ void wg_ss192(float (&d)[96], uint32_t alo, uint32_t ahi, uint32_t blo, uint32_t bhi, int sd) {
  asm volatile("{\n.reg .pred p;\n.reg .b64 da, db;\nsetp.ne.b32 p, %100, 0;\nmov.b64 da, {%96, %97};\nmov.b64 db, {%98, %99};\n"
    "wgmma.mma_async.sync.aligned.m64n192k16.f32.bf16.bf16 {%0,%1,%2,%3,%4,%5,%6,%7,%8,%9,%10,%11,%12,%13,%14,%15,%16,%17,%18,%19,%20,%21,%22,%23,%24,%25,%26,%27,%28,%29,%30,%31,%32,%33,%34,%35,%36,%37,%38,%39,%40,%41,%42,%43,%44,%45,%46,%47,%48,%49,%50,%51,%52,%53,%54,%55,%56,%57,%58,%59,%60,%61,%62,%63,%64,%65,%66,%67,%68,%69,%70,%71,%72,%73,%74,%75,%76,%77,%78,%79,%80,%81,%82,%83,%84,%85,%86,%87,%88,%89,%90,%91,%92,%93,%94,%95}, da, db, p, 1, 1, 0, 1;\n}\n"
    : "+f"(d[0]),"+f"(d[1]),"+f"(d[2]),"+f"(d[3]),"+f"(d[4]),"+f"(d[5]),"+f"(d[6]),"+f"(d[7]),"+f"(d[8]),"+f"(d[9]),"+f"(d[10]),"+f"(d[11]),"+f"(d[12]),"+f"(d[13]),"+f"(d[14]),"+f"(d[15]),"+f"(d[16]),"+f"(d[17]),"+f"(d[18]),"+f"(d[19]),"+f"(d[20]),"+f"(d[21]),"+f"(d[22]),"+f"(d[23]),"+f"(d[24]),"+f"(d[25]),"+f"(d[26]),"+f"(d[27]),"+f"(d[28]),"+f"(d[29]),"+f"(d[30]),"+f"(d[31]),"+f"(d[32]),"+f"(d[33]),"+f"(d[34]),"+f"(d[35]),"+f"(d[36]),"+f"(d[37]),"+f"(d[38]),"+f"(d[39]),"+f"(d[40]),"+f"(d[41]),"+f"(d[42]),"+f"(d[43]),"+f"(d[44]),"+f"(d[45]),"+f"(d[46]),"+f"(d[47]),"+f"(d[48]),"+f"(d[49]),"+f"(d[50]),"+f"(d[51]),"+f"(d[52]),"+f"(d[53]),"+f"(d[54]),"+f"(d[55]),"+f"(d[56]),"+f"(d[57]),"+f"(d[58]),"+f"(d[59]),"+f"(d[60]),"+f"(d[61]),"+f"(d[62]),"+f"(d[63]),"+f"(d[64]),"+f"(d[65]),"+f"(d[66]),"+f"(d[67]),"+f"(d[68]),"+f"(d[69]),"+f"(d[70]),"+f"(d[71]),"+f"(d[72]),"+f"(d[73]),"+f"(d[74]),"+f"(d[75]),"+f"(d[76]),"+f"(d[77]),"+f"(d[78]),"+f"(d[79]),"+f"(d[80]),"+f"(d[81]),"+f"(d[82]),"+f"(d[83]),"+f"(d[84]),"+f"(d[85]),"+f"(d[86]),"+f"(d[87]),"+f"(d[88]),"+f"(d[89]),"+f"(d[90]),"+f"(d[91]),"+f"(d[92]),"+f"(d[93]),"+f"(d[94]),"+f"(d[95])
    : "r"(alo), "r"(ahi), "r"(blo), "r"(bhi), "r"(sd));
}
template <int SD> __device__ __forceinline__ void wg_rs64t(float (&d)[32], uint32_t a0, uint32_t a1, uint32_t a2, uint32_t a3, uint32_t blo, uint32_t bhi) {
  asm volatile("{\n.reg .pred p;\n.reg .b64 db;\nsetp.ne.b32 p, %38, 0;\nmov.b64 db, {%36, %37};\n"
    "wgmma.mma_async.sync.aligned.m64n64k16.f32.bf16.bf16 {%0,%1,%2,%3,%4,%5,%6,%7,%8,%9,%10,%11,%12,%13,%14,%15,%16,%17,%18,%19,%20,%21,%22,%23,%24,%25,%26,%27,%28,%29,%30,%31}, {%32, %33, %34, %35}, db, p, 1, 1, 1;\n}\n"
    : "+f"(d[0]),"+f"(d[1]),"+f"(d[2]),"+f"(d[3]),"+f"(d[4]),"+f"(d[5]),"+f"(d[6]),"+f"(d[7]),"+f"(d[8]),"+f"(d[9]),"+f"(d[10]),"+f"(d[11]),"+f"(d[12]),"+f"(d[13]),"+f"(d[14]),"+f"(d[15]),"+f"(d[16]),"+f"(d[17]),"+f"(d[18]),"+f"(d[19]),"+f"(d[20]),"+f"(d[21]),"+f"(d[22]),"+f"(d[23]),"+f"(d[24]),"+f"(d[25]),"+f"(d[26]),"+f"(d[27]),"+f"(d[28]),"+f"(d[29]),"+f"(d[30]),"+f"(d[31])
    : "r"(a0), "r"(a1), "r"(a2), "r"(a3), "r"(blo), "r"(bhi), "n"(SD));
}
__device__ __forceinline__ void wg_rs64(float (&d)[32], uint32_t a0, uint32_t a1, uint32_t a2, uint32_t a3, uint32_t blo, uint32_t bhi, int sd) {
  asm volatile("{\n.reg .pred p;\n.reg .b64 db;\nsetp.ne.b32 p, %38, 0;\nmov.b64 db, {%36, %37};\n"
    "wgmma.mma_async.sync.aligned.m64n64k16.f32.bf16.bf16 {%0,%1,%2,%3,%4,%5,%6,%7,%8,%9,%10,%11,%12,%13,%14,%15,%16,%17,%18,%19,%20,%21,%22,%23,%24,%25,%26,%27,%28,%29,%30,%31}, {%32, %33, %34, %35}, db, p, 1, 1, 0;\n}\n"
    : "+f"(d[0]),"+f"(d[1]),"+f"(d[2]),"+f"(d[3]),"+f"(d[4]),"+f"(d[5]),"+f"(d[6]),"+f"(d[7]),"+f"(d[8]),"+f"(d[9]),"+f"(d[10]),"+f"(d[11]),"+f"(d[12]),"+f"(d[13]),"+f"(d[14]),"+f"(d[15]),"+f"(d[16]),"+f"(d[17]),"+f"(d[18]),"+f"(d[19]),"+f"(d[20]),"+f"(d[21]),"+f"(d[22]),"+f"(d[23]),"+f"(d[24]),"+f"(d[25]),"+f"(d[26]),"+f"(d[27]),"+f"(d[28]),"+f"(d[29]),"+f"(d[30]),"+f"(d[31])
    : "r"(a0), "r"(a1), "r"(a2), "r"(a3), "r"(blo), "r"(bhi), "r"(sd));
}
__device__ __forceinline__ void wg_rs32t(float (&d)[16], uint32_t a0, uint32_t a1, uint32_t a2, uint32_t a3, uint32_t blo, uint32_t bhi, int sd) {
  asm volatile("{\n.reg .pred p;\n.reg .b64 db;\nsetp.ne.b32 p, %22, 0;\nmov.b64 db, {%20, %21};\n"
    "wgmma.mma_async.sync.aligned.m64n32k16.f32.bf16.bf16 {%0,%1,%2,%3,%4,%5,%6,%7,%8,%9,%10,%11,%12,%13,%14,%15}, {%16, %17, %18, %19}, db, p, 1, 1, 1;\n}\n"
    : "+f"(d[0]),"+f"(d[1]),"+f"(d[2]),"+f"(d[3]),"+f"(d[4]),"+f"(d[5]),"+f"(d[6]),"+f"(d[7]),"+f"(d[8]),"+f"(d[9]),"+f"(d[10]),"+f"(d[11]),"+f"(d[12]),"+f"(d[13]),"+f"(d[14]),"+f"(d[15])
    : "r"(a0), "r"(a1), "r"(a2), "r"(a3), "r"(blo), "r"(bhi), "r"(sd));
}
__device__ __forceinline__ void wg_sps24(float (&d)[12], uint32_t alo, uint32_t ahi, uint32_t blo, uint32_t bhi, uint32_t meta, int sd) {
  asm volatile("{\n.reg .pred p;\n.reg .b64 da, db;\nsetp.ne.b32 p, %17, 0;\nmov.b64 da, {%12, %13};\nmov.b64 db, {%14, %15};\n"
    "wgmma.mma_async.sp.sync.aligned.m64n24k32.f32.bf16.bf16 {%0,%1,%2,%3,%4,%5,%6,%7,%8,%9,%10,%11}, da, db, %16, 0, p, 1, 1, 1, 1;\n}\n"
    : "+f"(d[0]),"+f"(d[1]),"+f"(d[2]),"+f"(d[3]),"+f"(d[4]),"+f"(d[5]),"+f"(d[6]),"+f"(d[7]),"+f"(d[8]),"+f"(d[9]),"+f"(d[10]),"+f"(d[11])
    : "r"(alo), "r"(ahi), "r"(blo), "r"(bhi), "r"(meta), "r"(sd));
}
__device__ __forceinline__ void wg_sp24t(float (&d)[12], uint32_t a0, uint32_t a1, uint32_t a2, uint32_t a3, uint32_t blo, uint32_t bhi, uint32_t meta, int sd) {
  asm volatile("{\n.reg .pred p;\n.reg .b64 db;\nsetp.ne.b32 p, %19, 0;\nmov.b64 db, {%16, %17};\n"
    "wgmma.mma_async.sp.sync.aligned.m64n24k32.f32.bf16.bf16 {%0,%1,%2,%3,%4,%5,%6,%7,%8,%9,%10,%11}, {%12, %13, %14, %15}, db, %18, 0, p, 1, 1, 1;\n}\n"
    : "+f"(d[0]),"+f"(d[1]),"+f"(d[2]),"+f"(d[3]),"+f"(d[4]),"+f"(d[5]),"+f"(d[6]),"+f"(d[7]),"+f"(d[8]),"+f"(d[9]),"+f"(d[10]),"+f"(d[11])
    : "r"(a0), "r"(a1), "r"(a2), "r"(a3), "r"(blo), "r"(bhi), "r"(meta), "r"(sd));
}

struct Cplx { float re, im; };
__device__ __forceinline__ Cplx cmul(Cplx a, Cplx b) { Cplx r; r.re = fmaf(a.re, b.re, -(a.im * b.im)); r.im = fmaf(a.re, b.im, a.im * b.re); return r; }
__device__ __forceinline__ Cplx cexp_e(float e, float ar, float ai) {
  float m = ex2f(e * ar), ph = e * ai;
  Cplx r; r.re = m * __cosf(ph); r.im = m * __sinf(ph); return r;
}
__device__ __forceinline__ void tma3d(uint32_t dst, const CUtensorMap* tm, int c1, int c2, uint32_t bar) {
  asm volatile("cp.async.bulk.tensor.3d.shared::cluster.global.mbarrier::complete_tx::bytes [%0], [%1, {%3, %4, %5}], [%2];"
               ::"r"(dst), "l"(tm), "r"(bar), "r"(0), "r"(c1), "r"(c2) : "memory");
}
__device__ __forceinline__ void tma2d_red(const CUtensorMap* tm, uint32_t src, int c0, int c1) {
  asm volatile("cp.reduce.async.bulk.tensor.2d.global.shared::cta.add.bulk_group [%0, {%2, %3}], [%1];" ::"l"(tm), "r"(src), "r"(c0), "r"(c1) : "memory");
}
__device__ __forceinline__ void tma3d_red(const CUtensorMap* tm, uint32_t src, int c1, int c2) {
  asm volatile("cp.reduce.async.bulk.tensor.3d.global.shared::cta.add.bulk_group [%0, {%2, %3, %4}], [%1];" ::"l"(tm), "r"(src), "r"(0), "r"(c1), "r"(c2) : "memory");
}
#define BULK_COMMIT() asm volatile("cp.async.bulk.commit_group;" ::: "memory")
#define OPAQUE(x) asm volatile("" : "+r"(x)::"memory")
__device__ __forceinline__ void publish(unsigned* p, unsigned v) {
  asm volatile("fence.proxy.async.global;" ::: "memory");
  asm volatile("red.release.gpu.global.add.u32 [%0], %1;" ::"l"(p), "r"(v) : "memory");
}

struct Tile { int mt, th, rank; };

template <int NB> __device__ __forceinline__ void ln_compute(uint32_t sb, uint32_t tin, int unit, const Params& P) {
  const int w8 = (threadIdx.x >> 5) & (40 / NB - 1), lane = threadIdx.x & 31, g = lane >> 2, q = lane & 3;
  const uint32_t tk = 4 * ((lane & 7) >> 1) + (lane & 1) + ((lane >> 2) & 2), red = sb + (NB == 5 ? MISC + 128 : STATS);
  mbar_wait(sb + BARS + 8 * (NB == 5 ? B_LI : B_LI2), 0);
  PROFC(w8 == 0 && NB == 5, 3);
  float piv[4], v[8];
  uint32_t x[5][4];
#pragma unroll
  for (int t = 0; t < 4; t++) { piv[t] = bf_lo(lds32(tin + (4 * q + t) * 128 + (((4 * q + t) & 7) << 4))); v[t] = 0.f; v[4 + t] = 0.f; }
  auto load = [&](int h) {
#pragma unroll
    for (int i = 0; i < 5; i++) {
      const uint32_t cb = 2 * NB * w8 + (lane >> 4) + 2 * i + h;
      ldsm4t(x[i], tin + tk * 128 + (cb >> 3) * 2048 + (((cb ^ tk) & 7) << 4));
    }
  };
#pragma unroll 1
  for (int h = 0; h < 2 * NB; h += 10) {
    load(h);
#pragma unroll
    for (int j = 0; j < 20; j++) {
      const int t = 2 * (j & 1);
      const float x0 = bf_lo(x[j >> 2][j & 3]) - piv[t], x1 = bf_hi(x[j >> 2][j & 3]) - piv[t + 1];
      v[t] += x0; v[t + 1] += x1; v[4 + t] = fmaf(x0, x0, v[4 + t]); v[5 + t] = fmaf(x1, x1, v[5 + t]);
    }
  }
#pragma unroll
  for (int h = 4; h; h >>= 1) {
    const bool up = g & h;
#pragma unroll
    for (int e = 0; e < h; e++) v[e] = (up ? v[e + h] : v[e]) + __shfl_xor_sync(0xffffffffu, up ? v[e] : v[e + h], h * 4);
  }
  sts32(red + lane * 32 + ((w8 ^ (NB == 5 ? lane & 4 : 0)) * 4), __float_as_uint(v[0]));
  PROFC(w8 == 0 && NB == 5, 4);
  bar_sync(NB == 5 ? 8 : 3, 1280 / NB);
  PROFC(w8 == 0 && NB == 5, 6);
  float s1, s2;
  {
    const uint4 a = lds128(red + lane * 32);
    s1 = (__uint_as_float(a.x) + __uint_as_float(a.y)) + (__uint_as_float(a.z) + __uint_as_float(a.w));
    if (NB == 5) {
      const uint4 b = lds128(red + lane * 32 + 16);
      s1 += (__uint_as_float(b.x) + __uint_as_float(b.y)) + (__uint_as_float(b.z) + __uint_as_float(b.w));
    }
    s2 = __shfl_xor_sync(0xffffffffu, s1, 16);
  }
  s1 *= (1.f / DM);
  const float pv = (g & 2) ? ((g & 1) ? piv[3] : piv[2]) : ((g & 1) ? piv[1] : piv[0]);
  const float var = fmaxf(fmaf(-s1, s1, s2 * (1.f / DM)), 0.f), mean = pv + s1;
  const float mb = bf_round(mean);
  const float sdv = bf_round(sqrt_fast(bf_round(bf_round(var) + 1e-5f)));
  const float r = rcp_fast(sdv), rh = bf_round(r);
  const uint32_t c0 = pack_bf16(-mb, rh), c1 = pack_bf16(r - rh, 0.f);
  uint32_t nm[2], rhi[2], rlo[2];
#pragma unroll
  for (int j = 0; j < 2; j++) {
    const uint32_t a = __shfl_sync(0xffffffffu, c0, q + 8 * j), b = __shfl_sync(0xffffffffu, c0, q + 8 * j + 4);
    nm[j] = __byte_perm(a, b, 0x5410); rhi[j] = __byte_perm(a, b, 0x7632);
    rlo[j] = __byte_perm(__shfl_sync(0xffffffffu, c1, q + 8 * j), __shfl_sync(0xffffffffu, c1, q + 8 * j + 4), 0x5410);
  }
  PROFC(w8 == 0 && NB == 5 && rlo[1] != 0x12345, 12);
  uint2* dst = (uint2*)(P.S->xnT + (size_t)(16 * NB * w8 + g) * SEQ + unit * 16) + q;
#pragma unroll 1
  for (int h = 2 * NB - 10; h >= 0; h -= 10) {
#pragma unroll
    for (int i = 0; i < 5; i++) {
#pragma unroll
      for (int j = 0; j < 4; j++) { const uint32_t c = hadd2(x[i][j], nm[j & 1]); x[i][j] = hfma2(c, rhi[j & 1], hmul2(c, rlo[j & 1])); }
      dst[(2 * i + h) * 2 * SEQ] = make_uint2(x[i][0], x[i][1]); dst[(2 * i + h + 1) * 2 * SEQ] = make_uint2(x[i][2], x[i][3]);
    }
    if (h) load(0);
  }
  if (w8 == 3) {
    const float sd2 = bf_round(sqrt_fast(bf_round(bf_round(var * r * r) + 1e-5f)));
    const float hr = 0.5f * r * rcp_fast(sd2);
    if (lane < 16) P.S->stats[unit * 16 + 4 * q + g] = make_float2(hr, -fmaf(bf_round((mean - mb) * r), sdv, mb) * hr);
  }
  __syncwarp();
  if (lane == 0) mbar_arrive(sb + BARS + 8 * B_LN);
  PROFC(w8 == 0 && NB == 5, 7);
}

__device__ __forceinline__ void store_x(uint32_t tin, int unit, const Maps& M) {
  asm volatile("cp.async.bulk.tensor.3d.global.shared::cta.bulk_group [%0, {%3, %2, %3}], [%1];" ::"l"(&M.Ol), "r"(tin), "r"(unit * 16), "r"(0) : "memory");
}
__device__ __forceinline__ void colsum(uint32_t sb, const Tile T, int mi, unsigned epoch, const Params& P) {
  const int tid = threadIdx.x & 127, warp = tid >> 5, lane = tid & 31;
  const int sub = lane / 9;
  if (T.th && tid >= 21 && tid < 60)
    asm volatile("cp.async.bulk.prefetch.L2.global [%0], 576;" ::"l"(P.w1 + (size_t)(T.mt * 40 + (tid < 40 ? tid : T.th * 20 - 60 + tid)) * FF + (tid < 40 ? T.th * 576 : 0) + T.rank * 288) : "memory");
#pragma unroll 1
  for (int part = T.th ? 0 : 2; part < 2; part++) {
    const int col = (part ? 0 : T.th * 576) + T.rank * 288 + (warp * 9 + lane - sub * 9) * 8, n = part ? 20 : 40;
    const uint4* wp = (const uint4*)(P.w1 + (size_t)(T.mt * 40 + (part ? T.th * 20 - 20 : 0) + min(sub, 2)) * FF + col);
    float c[8] = {0.f, 0.f, 0.f, 0.f, 0.f, 0.f, 0.f, 0.f};
#pragma unroll 1
    for (int h = 0; h < n; h += 21) {
      uint4 v[7];
#pragma unroll
      for (int j = 0; j < 7; j++) v[j] = (j < 6 || h + 18 + sub < n) ? __ldg(wp + (h + 3 * j) * (FF / 8)) : make_uint4(0, 0, 0, 0);
#pragma unroll
      for (int j = 0; j < 7; j++) {
        c[0] += bf_lo(v[j].x); c[1] += bf_hi(v[j].x); c[2] += bf_lo(v[j].y); c[3] += bf_hi(v[j].y);
        c[4] += bf_lo(v[j].z); c[5] += bf_hi(v[j].z); c[6] += bf_lo(v[j].w); c[7] += bf_hi(v[j].w);
      }
    }
#pragma unroll
    for (int e = 0; e < 8; e++) c[e] += __shfl_down_sync(0xffffffffu, c[e], 9) + __shfl_down_sync(0xffffffffu, c[e], 18);
    if (sub == 0) {
      float* o = P.S->csp[epoch & 1] + col;
      asm volatile("red.relaxed.gpu.global.add.v4.f32 [%0], {%1,%2,%3,%4};" ::"l"(o), "f"(c[0]), "f"(c[1]), "f"(c[2]), "f"(c[3]) : "memory");
      asm volatile("red.relaxed.gpu.global.add.v4.f32 [%0], {%1,%2,%3,%4};" ::"l"(o + 4), "f"(c[4]), "f"(c[5]), "f"(c[6]), "f"(c[7]) : "memory");
    }
  }
  if (tid < 18) P.S->csp[~epoch & 1][mi * 18 + tid] = 0.f;
  if (tid == 0) P.S->epoch[blockIdx.x * 4 + 3] = epoch;
  __syncwarp();
  if (lane == 0) mbar_arrive(sb + BARS + 8 * B_CS);
  PROFC(tid == 0, 28);
}

struct GeluC { uint32_t tcs, rdst, rbar; float hr0, nm0, hr1, nm1; };
__device__ __forceinline__ void gelu_pre(uint32_t (&hp)[4], uint32_t (&z)[4], const float* acc, const uint4 (&t)[2], const GeluC& c) {
  const uint32_t C0 = 0x3fcc3fccu, C1 = 0x3e923e92u;
#pragma unroll
  for (int e = 0; e < 4; e++) {
    const uint4 tt = t[e >> 1];
    const float hr = (e & 1) ? c.hr1 : c.hr0, nm = (e & 1) ? c.nm1 : c.nm0;
    hp[e] = pack_bf16(fmaf(acc[2 * e], hr, fmaf(nm, __uint_as_float(tt.x), __uint_as_float(tt.z))),
                      fmaf(acc[2 * e + 1], hr, fmaf(nm, __uint_as_float(tt.y), __uint_as_float(tt.w))));
    z[e] = hmul2(hp[e], hfma2(hmul2(hp[e], hp[e]), C1, C0));
  }
}
template <int N> __device__ __forceinline__ void gelu_run(const float* acc, uint32_t (*hA)[4], uint32_t to, uint32_t ro, const GeluC& c) {
  uint4 t[2][2];
  uint32_t hp[2][4], z[2][4];
  t[0][0] = lds128n(c.tcs + to); t[0][1] = lds128n(c.tcs + to + 64);
  t[1][0] = lds128n(c.tcs + to + 128); t[1][1] = lds128n(c.tcs + to + 192);
  gelu_pre(hp[0], z[0], acc, t[0], c);
#pragma unroll
  for (int s = 0; s < N; s++) {
    const int b = s & 1;
    if (s + 2 < N) { t[b][0] = lds128n(c.tcs + to + (s + 2) * 128); t[b][1] = lds128n(c.tcs + to + (s + 2) * 128 + 64); }
#pragma unroll
    for (int e = 0; e < 4; e++) asm("tanh.approx.bf16x2 %0, %0;" : "+r"(z[b][e]));
    if (s + 1 < N) gelu_pre(hp[b ^ 1], z[b ^ 1], acc + 8 * (s + 1), t[b ^ 1], c);
#pragma unroll
    for (int e = 0; e < 4; e++) hA[s][e] = hfma2(hp[b][e], z[b][e], hp[b][e]);
    asm volatile("st.async.weak.shared::cluster.mbarrier::complete_tx::bytes.v4.b32 [%0], {%1,%2,%3,%4}, [%5];"
                 ::"r"(c.rdst + ro + s * 2048), "r"(hA[s][0]), "r"(hA[s][1]), "r"(hA[s][2]), "r"(hA[s][3]), "r"(c.rbar));
  }
}

__device__ __forceinline__ void mlp_role(uint32_t sb, int wg, const Tile T, const Params& P, const Maps& M) {
  const int rank = T.rank;
  const int tid = threadIdx.x & 127, warp = tid >> 5, lane = tid & 31, g = lane >> 2, q = lane & 3;
  const uint32_t bars = sb + BARS, sd = (sb & 0x3FFFF) >> 4, zone = sb + ZONE + wg * ZSZ;
  uint32_t hA[36][4];
  int slot = 0, ph = 0;
  auto release = [&]() { if (tid == 0) mbar_arrive(bars + 8 * (B_EMPTY + (slot == 0 ? NSLOT - 1 : slot - 1))); };
  {
    float acc[96], acc3[48];
    const uint32_t xr = (sd + ((wg ? XR1 : XR0) >> 4)) | (1u << 16);
    const uint32_t w0 = sd | ((4096u >> 4) << 16);
    int xs = 0, xp = 0;
#pragma unroll 1
    for (int s = 0; s < 20; s++) {
      if (!(s & 1)) mbar_wait(bars + 8 * (B_XF + wg * 3 + xs), xp);
      mbar_wait(bars + 8 * (B_FULL + slot), ph);
      PROFC(tid == 0, 32 + wg * 68 + s);
      const uint32_t xa = xr + xs * 512 + (s & 1) * 4, so = slot * (SLOT >> 4);
      WG_FENCE();
#pragma unroll
      for (int kk = 0; kk < 2; kk++) {
        wg_ss192(acc, xa + kk * 2, HI_SW128, w0 + so + kk * 128, HI_SW128, (s | kk) != 0);
        wg_ss96(acc3, xa + kk * 2, HI_SW128, w0 + so + 768 + kk * 128, HI_SW128, (s | kk) != 0);
      }
      WG_COMMIT();
      WG_WAIT(1);
      if (s) release();
      if (s & 1) { if (++xs == 3) { xs = 0; xp ^= 1; } }
      else if (s && tid == 0) mbar_arrive(bars + 8 * (B_XE + wg * 3 + (xs == 0 ? 2 : xs - 1)));
      if (++slot == NSLOT) { slot = 0; ph ^= 1; }
    }
    WG_WAIT(0);
    release();
    PROFC(tid == 0, 8 + wg);
    mbar_wait(bars + 8 * B_TAB, 0);
    if (tid == 0) mbar_arrive_cluster(mapa(bars + 8 * (B_HRDY + wg), rank ^ 1));
    const int r0 = wg * 64 + warp * 16 + g;
    GeluC c;
    {
      uint32_t a, b;
      asm volatile("ld.shared.v2.u32 {%0,%1}, [%2];" : "=r"(a), "=r"(b) : "r"(sb + STATS + r0 * 8));
      c.hr0 = __uint_as_float(a); c.nm0 = __uint_as_float(b);
      asm volatile("ld.shared.v2.u32 {%0,%1}, [%2];" : "=r"(a), "=r"(b) : "r"(sb + STATS + r0 * 8 + 64));
      c.hr1 = __uint_as_float(a); c.nm1 = __uint_as_float(b);
    }
    c.rdst = mapa(zone + tid * 16, rank ^ 1);
    c.rbar = mapa(bars + 8 * (B_HIN + wg), rank ^ 1);
    c.tcs = sb + TCS + q * 16;
    mbar_wait_cluster(bars + 8 * (B_HRDY + wg), 0);
    OPAQUE(c.tcs);
    gelu_run<6>(acc3, hA + 12, 1536, 12 * 2048, c);
    gelu_run<12>(acc, hA, 0, 0, c);
  }
  PROFC(tid == 0, 10 + wg);
  float acc[32];
  auto unit = [&](int p, int n) {
    mbar_wait(bars + 8 * (B_FULL + slot), ph);
    const uint32_t wb = (sd + slot * (SLOT >> 4)) | (1u << 16);
    WG_FENCE();
#pragma unroll
    for (int kk = 0; kk < 4 * n; kk++) {
      if (p == 0 && kk == 0) wg_rs64t<0>(acc, hA[0][0], hA[0][1], hA[0][2], hA[0][3], wb, HI_SW128);
      else wg_rs64t<1>(acc, hA[p * 4 + kk][0], hA[p * 4 + kk][1], hA[p * 4 + kk][2], hA[p * 4 + kk][3], n == 1 ? wb + (kk & 1) * 128 + ((kk >> 1) ^ rank) * 256 : wb + kk * 128, HI_SW128);
    }
    WG_COMMIT();
    if (p > 0) { WG_WAIT(1); release(); }
    if (++slot == NSLOT) { slot = 0; ph ^= 1; }
  };
  int dj = 2 * T.th;
#pragma unroll 1
  for (int a = 0; a < 5; a++) {
    if (a == 0 && wg) bar_sync(9, 256);
    unit(0, 2); unit(2, 2);
    if (a == 0) {
      if (!wg) bar_arrive(9, 256);
      mbar_wait_cluster(bars + 8 * (B_HIN + wg), 0);
#pragma unroll
      for (int kk = 0; kk < 18; kk++) {
        const uint4 v = lds128(zone + tid * 16 + (kk < 2 ? 16 + kk : kk - 2) * 2048);
        hA[18 + kk][0] = v.x; hA[18 + kk][1] = v.y; hA[18 + kk][2] = v.z; hA[18 + kk][3] = v.w;
      }
      bar_sync(1 + wg, 128);
      if (lane == 0) mbar_arrive(bars + 8 * B_HFREE);
      mbar_wait(bars + 8 * B_OUT, 0);
    }
    unit(4, 1); unit(5, 2); unit(7, 2);
    if (lane == 0) asm volatile("cp.async.bulk.wait_group.read 1;" ::: "memory");
    WG_WAIT(0);
    release();
    PROFC(tid == 0, 88 + wg * 5 + a);
    const uint32_t st = zone + warp * 4096 + (a & 1) * 2048, row = st + (lane & 15) * 128;
    __syncwarp();
#pragma unroll
    for (int jj = 0; jj < 4; jj++)
      stsm4(row + (((2 * jj + (lane >> 4)) ^ (lane & 7)) << 4), pack_bf16(acc[8 * jj], acc[8 * jj + 1]), pack_bf16(acc[8 * jj + 2], acc[8 * jj + 3]),
            pack_bf16(acc[8 * jj + 4], acc[8 * jj + 5]), pack_bf16(acc[8 * jj + 6], acc[8 * jj + 7]));
    fence_async_smem();
    __syncwarp();
    if (lane == 0) { tma2d_red(&M.O, st, (rank * 5 + dj) * 64, T.mt * 128 + wg * 64 + warp * 16); BULK_COMMIT(); }
    if (++dj == 5) dj = 0;
  }
  if (lane == 0) asm volatile("cp.async.bulk.wait_group.read 0;" ::: "memory");
  if (tid == 0) { PROF(14 + wg); }
}

__device__ __forceinline__ Cplx cmulc(Cplx a, Cplx b) { Cplx r; r.re = fmaf(a.re, b.re, a.im * b.im); r.im = fmaf(a.im, b.re, -(a.re * b.im)); return r; }
__device__ __forceinline__ float lds_bf(uint32_t a) { unsigned short v; asm volatile("ld.shared.u16 %0, [%1];" : "=h"(v) : "r"(a) : "memory"); return __uint_as_float((uint32_t)v << 16); }
__device__ __forceinline__ void bulk_ld(uint32_t dst, const void* src, uint32_t n, uint32_t bar) {
  asm volatile("cp.async.bulk.shared::cluster.global.mbarrier::complete_tx::bytes [%0], [%1], %2, [%3];" ::"r"(dst), "l"(src), "r"(n), "r"(bar) : "memory");
}
__device__ __forceinline__ void load_par(uint32_t dst, uint32_t bar, int pair, const Params& P) {
  mbar_expect(bar, 3072);
#pragma unroll 1
  for (int i = 0; i < 6; i++) bulk_ld(dst + i * 512, (&P.Are)[i] + pair * 256, 512, bar);
}
__device__ __forceinline__ void prefetch_l2(const void* p, uint32_t n) { asm volatile("cp.async.bulk.prefetch.L2.global [%0], %1;" ::"l"(p), "r"(n) : "memory"); }
__device__ __forceinline__ uint32_t ld_dt(const Params& P, int pair) {
  uint32_t a;
  const __nv_bfloat16 *p0 = P.logdt, *p1 = P.dskip;
  asm volatile("" : "+l"(p0), "+l"(p1));
  asm volatile("ld.global.nc.u16 %0, [%1];" : "=r"(a) : "l"(((threadIdx.x & 1) ? p1 : p0) + 2 * pair + ((threadIdx.x >> 6) & 1)));
  return a;
}
__device__ __forceinline__ int uni(int v) { return __shfl_sync(0xffffffffu, v, 0); }
template <int N> __device__ __forceinline__ void toep(uint32_t (&A)[4][4], uint32_t ta) {
  OPAQUE(ta);
  A[0][2] = lds32n(ta);
#pragma unroll
  for (int i = 0; i < N; i++) {
    A[i][0] = lds32n(ta + 32 * i + 16); A[i][1] = lds32n(ta + 32 * i + 32);
    if (i) asm volatile("mov.b32 %0, %1;" : "=r"(A[i][2]) : "r"(A[i - 1][1]));
    asm volatile("mov.b32 %0, %1;" : "=r"(A[i][3]) : "r"(A[i][0]));
  }
}

template <bool LOW>
__device__ __forceinline__ void kgen_stream(uint32_t sb, uint32_t cw, uint32_t ub, int wg, int sp, int nk, uint32_t xbar, uint32_t ld0, uint32_t ld1) {
  const uint32_t cd = (cw & 0x3FFFF) >> 4;
  const int nb = 4 + wg;
  {
    const int tid = threadIdx.x & 127, g = (tid >> 2) & 7, q = tid & 3;
    uint32_t md = 0;
    if (tid < 80) sts128(cw + 384 + (tid >= 40 ? 4480 : 0) + tid * 16, 0, 0, 0, 0);
#pragma unroll 1
    for (int n = 0; n < 8; n++) {
      const int kk = 8 * (q & 1) + 2 * (n & 3), rho = g + 8 * (n >> 2);
      md |= (kk < rho ? 8u : kk == rho ? 12u : 13u) << (4 * n);
    }
    if (tid < 32) sts32(cw + tid * 4, md);
  }
#pragma unroll 1
  for (int ik = nk - 1; ik >= 0; ik--) {
    {
      int tid = threadIdx.x & 127;
      OPAQUE(tid);
      const int warp = tid >> 5, lane = tid & 31, g = lane >> 2, q = lane & 3;
      const int kch = tid >> 6, kmu = tid & 63;
      const uint32_t tabs = ik ? sb + C_S + sp * 2 * TCH : cw + C_T;
      uint32_t meta = warp < 2 ? 0x44444444u : 0xEEEEEEEEu;
      float kacc[12] = {0.f, 0.f, 0.f, 0.f, 0.f, 0.f, 0.f, 0.f, 0.f, 0.f, 0.f, 0.f};
      for (uint32_t a = tid * 16; a < 2 * TCH; a += 2048) sts128(tabs + a, 0, 0, 0, 0);
      PROFC(threadIdx.x == 384, 65);
      mbar_wait(ub + 16 + 8 * ik, 0);
      PROFC(threadIdx.x == 384, 67);
      const float dt = bf_round(expf(bf_lo(__shfl_sync(0xffffffffu, ik ? ld1 : ld0, 0)))), dsk = bf_lo(__shfl_sync(0xffffffffu, ik ? ld1 : ld0, 1));
      PROFC(threadIdx.x == 384, 64);
#pragma unroll 1
      for (int ck = 0; ck < 2; ck++) {
        const uint32_t pp = cw + C_U + ik * 5120 + kch * 256 + ck * 128 + kmu * 2;
        const float ar = dt * lds_bf(pp) * 1.4426950408889634f, ai = dt * lds_bf(pp + 512);
        const float br = dt * lds_bf(pp + 1024), bi = dt * lds_bf(pp + 1536), cre = lds_bf(pp + 2048), cim = lds_bf(pp + 2560);
        const Cplx z = cexp_e(1.f, ar, ai), z8 = cexp_e(8.f, ar, ai), z64 = cexp_e(64.f, ar, ai);
        const Cplx z128 = cmul(z64, z64), w = cmul(z128, z128);
        uint32_t Ar[4], Ai[4], Br[12], Bi[12];
        const uint32_t aa = cw + C_KA + (kmu >> 3) * 2080 + (kmu & 4) * 260 + (kmu & 3) * 32 + kch * 512;
        if (LOW) { WG_WAIT(0); mbar_wait(xbar, 0); bar_sync(nb, 128); }
        {
          Cplx e0, e1;
          e0.re = 1.f; e0.im = 0.f; e1.re = z8.re; e1.im = -z8.im;
#pragma unroll
          for (int j = 0; j < 4; j++) {
            Ar[j] = pack_bf16(e0.re, e1.re); Ai[j] = pack_bf16(e0.im, e1.im);
            if (j < 3) { e0 = cmulc(e1, z8); e1 = cmulc(e0, z8); }
          }
        }
        if (!LOW) {
          asm volatile("" ::"r"(Ar[3]), "r"(Ai[3]), "f"(w.re), "f"(w.im) : "memory");
          WG_WAIT(0);
          bar_sync(nb, 128);
        }
        sts128(aa, Ar[0], Ar[1], Ar[2], Ar[3]); sts128(aa + 16, Ai[0], Ai[1], Ai[2], Ai[3]);
        {
          Cplx f = z64;
#pragma unroll 1
          for (int m = 128; m < 512; m += 128) {
            const uint32_t fr = pack_bf16(f.re, f.re), fi = pack_bf16(f.im, f.im), fn = fi ^ 0x80008000u;
            sts128(aa + m, hfma2(Ar[0], fr, hmul2(Ai[0], fi)), hfma2(Ar[1], fr, hmul2(Ai[1], fi)), hfma2(Ar[2], fr, hmul2(Ai[2], fi)), hfma2(Ar[3], fr, hmul2(Ai[3], fi)));
            sts128(aa + m + 16, hfma2(Ai[0], fr, hmul2(Ar[0], fn)), hfma2(Ai[1], fr, hmul2(Ar[1], fn)), hfma2(Ai[2], fr, hmul2(Ar[2], fn)), hfma2(Ai[3], fr, hmul2(Ar[3], fn)));
            f = cmul(f, z64);
          }
        }
        {
#define KP(j, u, v) do { Br[j] = pack_bf16((u).re, (v).re); Bi[j] = pack_bf16((u).im, (v).im); } while (0)
          Cplx p0, p1, s, t;
          p0.re = cre * br - cim * bi; p0.im = cre * bi + cim * br;
          t = cmul(p0, w); KP(10, t, t);
          p1 = cmul(p0, z); KP(0, p0, p1);
          p0 = cmul(p1, z); p1 = cmul(p0, z); KP(1, p0, p1); s = cmul(p0, w);
          p0 = cmul(p1, z); p1 = cmul(p0, z); KP(2, p0, p1); t = cmul(p0, w); KP(4, s, t);
          p0 = cmul(p1, z); p1 = cmul(p0, z); KP(3, p0, p1); s = cmul(p0, w);
          p1 = cmul(cmul(p1, z), w); KP(5, s, p1);
          t = cmul(t, w); p1 = cmul(p1, w); KP(6, t, p1);
          t = cmul(t, w); p1 = cmul(p1, w); KP(7, t, p1);
          p0 = cmul(p1, w); p1 = cmul(p0, w); KP(8, p0, p1);
          p0 = cmul(p1, w); p1 = cmul(p0, w); KP(9, p0, p1);
          Br[11] = Br[10]; Bi[11] = Bi[10];
#undef KP
        }
        const uint32_t ba = cw + C_KB + (kmu >> 1) * 400 + (kmu & 1) * 64 + kch * 32;
#pragma unroll
        for (int m = 0; m < 3; m++) {
          sts128(ba + m * 128, Br[4 * m], Br[4 * m + 1], Br[4 * m + 2], Br[4 * m + 3]);
          sts128(ba + m * 128 + 16, Bi[4 * m], Bi[4 * m + 1], Bi[4 * m + 2], Bi[4 * m + 3]);
        }
        fence_async_smem();
        bar_sync(nb, 128);
        PROFC(threadIdx.x == 384, 66 + 3 * ck);
        OPAQUE(meta);
        WG_FENCE();
#pragma unroll
        for (int j = 0; j < 8; j++)
          wg_sps24(kacc, (cd + ((C_KA + j * 2080) >> 4)) | ((1040u >> 4) << 16), HI_KG, (cd + ((C_KB + j * 1600) >> 4)) | ((400u >> 4) << 16), HI_KG, meta, ck | j);
        WG_COMMIT();
      }
      WG_WAIT(0);
      PROFC(threadIdx.x == 384, 72);
      const uint32_t tab = tabs + (warp >> 1) * TCH;
      if (lane == 0 && !(warp & 1)) kacc[0] += dsk;
      if (lane == 31 && (warp & 1)) sts32(tab, __float_as_uint(kacc[7]));
#pragma unroll 1
      for (int hf = 0; hf < 2; hf++) {
        const int i = 16 * (warp & 1) + g + 8 * hf;
        const uint32_t w1 = pack_bf16(kacc[5], kacc[4]), w2 = pack_bf16(kacc[8], kacc[9]);
        sts32(tab + 2 * (T_B0 + 8 * i + 2 * q), pack_bf16(kacc[1], kacc[0]));
        kacc[0] = kacc[2]; kacc[1] = kacc[3]; kacc[4] = kacc[6]; kacc[5] = kacc[7]; kacc[8] = kacc[10]; kacc[9] = kacc[11];
        if (q < 2) {
          uint32_t a = tab + 2 * (T_B1 + 8 * i + 2 + 4 * q);
          sts32(a, w1); sts32(a + 4, __byte_perm(w1, 0, 0x1010));
          if (lane == 29 && i == 31) sts32(a + 8, w1 << 16);
          a = tab + 2 * (((i & 1) ? T_F9 : T_F7) + 32 * q + ((i >> 1) ^ 1));
          sts16(a, w2); sts16(a + 32, w2 >> 16);
        } else {
          const uint32_t a = tab + 2 * (32 * q - 128 + (i ^ 1));
          sts16(a + 2 * T_C5, w1); sts16(a + 2 * T_C5 + 128, w1); sts16(a + 2 * T_C3, w1 >> 16); sts16(a + 2 * T_C3 + 128, w1 >> 16);
          if (lane == 2 && i == 0) sts32(tab + 2 * T_B1, __byte_perm(w2, 0, 0x1010));
        }
      }
      bar_sync(nb, 128);
#pragma unroll
      for (int ch = 0; ch < 2; ch++) {
        const uint32_t a = tabs + ch * TCH + 64 + tid * 16;
        const uint4 v = lds128(a);
        const uint32_t pr = lds32(a - 4);
        sts128(a + TCP, __byte_perm(v.x, pr, 0x5432), __byte_perm(v.y, v.x, 0x5432), __byte_perm(v.z, v.y, 0x5432), __byte_perm(v.w, v.z, 0x5432));
      }
      if (ik) mbar_arrive(sb + BARS + 8 * (B_SP + sp));
      else {
        sts128(cw + C_X5 + (tid >> 6) * 6912 + ((tid >> 2) & 15) * 144 + (tid & 3) * 32 + 16, 0, 0, 0, 0);
        if (tid == 0) sts128(cw + C_X9, 0, 0, 0, 0);
        bar_sync(nb, 128);
      }
      PROFC(tid == 0, 20 + wg);
    }
  }
}
template <bool LOW>
__device__ __forceinline__ void conv_stream(uint32_t sb, uint32_t cw, uint32_t ub, int wg, int p0, int ps, int p6, uint32_t prog, unsigned target,
                                            const Params& P, const Maps& M) {
  const uint32_t cd = (cw & 0x3FFFF) >> 4;
  const int nb = 4 + wg;
  if ((threadIdx.x & 127) == 32) {
    if (target) { poll_ge(&P.S->cnt1, target); PROF(18); }
    asm volatile("fence.proxy.async;" ::: "memory");
    mbar_expect(ub, 4096);
    tma2d(cw + C_U, &M.U, 0, p0 * 128, ub);
  }
  __syncwarp();
#define PRC(n) PROFC(threadIdx.x == 384 && nch == 1, 74 + n)
  int prev = 0;
#pragma unroll 1
  for (int nch = 0; prog; prog >>= 4, nch++) {
    {
      int tid = threadIdx.x & 127;
      OPAQUE(tid);
      const int warp = tid >> 5, lane = tid & 31, g = lane >> 2, q = lane & 3;
      const int code = uni((prog & 15) - 1), odd = uni(nch & 1);
      const int chan = 2 * (code < 2 ? p0 : code < 6 ? p0 + (3 + (code >> 1) - wg) * ps : p6) + (code & 1);
      const uint32_t u = cw + C_U + odd * 5120, tab = (code < 2 ? cw + C_T : sb + C_S - 2 * TCH) + code * TCH;
      if (tid == 32 && prog > 15) {
        const int nx = (prog >> 4 & 15) - 1;
        mbar_expect(ub + 8 - odd * 8, 4096);
        tma2d(cw + C_U + 5120 - odd * 5120, &M.U, 0, (2 * (nx < 2 ? p0 : nx < 6 ? p0 + (3 + (nx >> 1) - wg) * ps : p6) + (nx & 1)) * 64, ub + 8 - odd * 8);
      }
      if (code >= 2) mbar_wait(sb + BARS + 8 * (B_SP - 1 + (code >> 1)), 0);
      PRC(0);
      uint32_t tp = tab + ((g & 1) ? -2 : (int)TCP) + 2 * (g - 2 * q);
      OPAQUE(tp);
      float a1[32] = {}, a2[12] = {}, a3[16] = {};
      uint32_t A[4][4], B_[4][4];
      uint32_t (&B)[4][4] = LOW ? A : B_;
#define CWAIT() do { if (LOW) WG_WAIT(0); else WG_WAIT(1); } while (0)
      const uint32_t t1 = tp + 32 * (warp & 1) + 2 * (((warp >> 1) ? T_B1 : T_B0) - 24);
      const uint32_t ud = ((((u + 32) & 0x3FFFF) >> 4)) | (1u << 16);
#define SET1(Q, n, s0) do { toep<n>(Q, t1 + 32 * (s0)); WG_FENCE(); \
        _Pragma("unroll") for (int i = 0; i < n; i++) wg_rs64(a1, Q[i][0], Q[i][1], Q[i][2], Q[i][3], ud - 2 * ((s0) + i), HI_SW64, (s0) + i); WG_COMMIT(); } while (0)
      mbar_wait(ub + odd * 8, (nch >> 1) & 1);
      PRC(1);
      if (!LOW) SET1(A, 3, 0);
      if (tid < ((ABL & 1) ? 0 : 96)) {
        uint32_t w[14], o[12], W[10];
        {
          const uint32_t a = sw64(u + tid * 32), b = sw64(u + tid * 32 - 32);
          uint4 v;
          asm volatile("ld.shared.v2.u32 {%0,%1}, [%2];" : "=r"(w[0]), "=r"(w[1]) : "r"(b + 8) : "memory");
          v = lds128(b ^ 16); w[2] = v.x; w[3] = v.y; w[4] = v.z; w[5] = v.w;
          v = lds128(a); w[6] = v.x; w[7] = v.y; w[8] = v.z; w[9] = v.w;
          v = lds128(a ^ 16); w[10] = v.x; w[11] = v.y; w[12] = v.z; w[13] = v.w;
        }
#pragma unroll
        for (int k = 0; k < 12; k++) o[k] = __byte_perm(w[k], w[k + 1], 0x5432);
#pragma unroll
        for (int k = 0; k < 10; k++) W[k] = hadd2(w[k + 2], hadd2(o[k + 1], o[k + 2]));
        const uint32_t xi = cw + C_X5 + (tid >> 1) * 144 + (tid & 1) * 64;
        sts128(xi + 6912, W[2], W[3], W[4], W[5]); sts128(xi + 6912 + 32, W[6], W[7], W[8], W[9]);
        if (tid < 64) { sts128(xi + 6912 + 2320, W[2], W[3], W[4], W[5]); sts128(xi + 6912 + 2352, W[6], W[7], W[8], W[9]); }
#pragma unroll
        for (int k = 0; k < 8; k++) W[k] = hadd2(W[k], hadd2(w[k + 1], w[k + 3]));
        sts128(xi, W[0], W[1], W[2], W[3]); sts128(xi + 32, W[4], W[5], W[6], W[7]);
        if (tid < 64) {
          sts128(xi + 2320, W[0], W[1], W[2], W[3]); sts128(xi + 2352, W[4], W[5], W[6], W[7]);
#pragma unroll
          for (int k = 0; k < 8; k++) W[k] = hadd2(W[k], hadd2(o[k], o[k + 3]));
          const uint32_t x7 = sw32(cw + C_X7 + tid * 32);
          sts128(x7, W[0], W[1], W[2], W[3]);
          sts128(x7 ^ 16, W[4], W[5], W[6], W[7]);
#pragma unroll
          for (int k = 0; k < 8; k++) W[k] = hadd2(W[k], hadd2(w[k], w[k + 4]));
          sts128((x7 ^ 16) + 2048, W[0], W[1], W[2], W[3]);
          if (tid < 63) sts128(sw32(cw + C_X9 + tid * 32 + 32), W[4], W[5], W[6], W[7]);
        }
      }
      fence_async_smem();
      PRC(2);
      if (LOW) {
        SET1(A, 1, 0);
#pragma unroll 1
        for (int s0 = 1; s0 < 19; s0 += 2) { SET1(B_, 1, s0); WG_WAIT(1); SET1(A, 1, s0 + 1); WG_WAIT(1); }
      } else {
#pragma unroll 1
        for (int s0 = 3; s0 < 19; s0 += 8) { SET1(B, 4, s0); WG_WAIT(1); SET1(A, 4, s0 + 4); WG_WAIT(1); }
      }
      if (lane == 0) asm volatile("cp.async.bulk.wait_group 0;" ::: "memory");
      bar_sync(nb, 128);
      PRC(3);
      if (tid == 96 && nch) asm volatile("red.relaxed.gpu.global.add.u32 [%0], 1;" ::"l"(P.S->ycnt + prev * 32) : "memory");
      prev = chan >> 6;
      auto y3 = [&]() {
      stsm4(sw128(cw + C_Y3 + 32 * (8 * warp + (lane & 7)) + (lane >> 4) * 1024 + (lane & 8) * 2),
            pack_bf16(a3[0], a3[1]), pack_bf16(a3[4], a3[5]), pack_bf16(a3[2] + a3[8], a3[3] + a3[9]), pack_bf16(a3[6] + a3[12], a3[7] + a3[13]));
      };
      auto set3 = [&]() {
      OPAQUE(tp);
#pragma unroll
      for (int i = 0; i < 4; i++) {
        const uint32_t a = tp + 16 * warp + 2 * ((i >> 1) ? T_F9 : T_F7) - 32 * (i & 1);
        B[i][0] = lds32n(a); B[i][1] = lds32n(a + 64); B[i][2] = lds32n(a - 16); B[i][3] = lds32n(a + 48);
      }
      WG_FENCE();
#pragma unroll
      for (int i = 0; i < 4; i++)
        wg_rs32t(a3, B[i][0], B[i][1], B[i][2], B[i][3], (cd + (((i >> 1) ? C_X9 : C_X7) >> 4) + 32 * (i & 1)) | ((1024u >> 4) << 16), HI_SW32, i);
      WG_COMMIT();
      };
      if (LOW) WG_WAIT(0); else { set3(); WG_WAIT(1); }
      PRC(4);
      {
        const uint32_t y1 = cw + C_Y1 + (warp >> 1) * 4096 + 64 * ((lane & 7) + (lane >> 4) * 8) + 32 * (warp & 1) + (lane & 8) * 2;
#pragma unroll
        for (int j = 0; j < 4; j++)
          stsm4t(sw128(y1) + 1024 * j, pack_bf16(a1[8 * j], a1[8 * j + 1]), pack_bf16(a1[8 * j + 2], a1[8 * j + 3]),
                 pack_bf16(a1[8 * j + 4], a1[8 * j + 5]), pack_bf16(a1[8 * j + 6], a1[8 * j + 7]));
        fence_async_smem();
        if (warp) bar_arrive(nb + 6, 128);
      }
      if (LOW) { set3(); WG_WAIT(0); y3(); }
      const uint32_t x5 = (cd + (C_X5 >> 4)) | ((144u >> 4) << 16);
      uint32_t mt[4];
      const uint32_t md = lds32(cw + lane * 4);
#pragma unroll
      for (int i = 0; i < 4; i++) { mt[i] = 3 - i < warp ? 0x88888888u : 3 - i == warp ? md : 0xDDDDDDDDu; OPAQUE(mt[i]); }
      toep<4>(A, tp + 32 * warp + 2 * (T_C5 - 56));
      WG_FENCE();
#pragma unroll
      for (int i = 0; i < 4; i++) wg_sp24t(a2, A[i][0], A[i][1], A[i][2], A[i][3], x5 + 36 * (3 - i), HI_XI, mt[i], i);
      WG_COMMIT();
      if (warp == 0) {
        bar_sync(nb + 6, 128);
        if (lane == 0) {
          asm volatile("cp.async.bulk.tensor.3d.global.shared::cta.bulk_group [%0, {%2, %2, %3}], [%1];" ::"l"(&M.Yr), "r"(cw + C_Y1), "r"(0), "r"(chan) : "memory");
          BULK_COMMIT();
        }
        __syncwarp();
      }
      CWAIT();
      toep<4>(B, tp + 32 * warp + 2 * (T_C3 - 56));
      WG_FENCE();
#pragma unroll
      for (int i = 0; i < 4; i++) wg_sp24t(a2, B[i][0], B[i][1], B[i][2], B[i][3], x5 + (6912 >> 4) + 36 * (3 - i), HI_XI, mt[i], 1);
      WG_COMMIT();
      if (!LOW) y3();
      {
        const float f1024 = __uint_as_float(lds32(tab));
        const uint32_t a = u + 256 * warp + 4 * lane - 8;
        float fx[8];
#pragma unroll
        for (int i = 0; i < 4; i++) {
          const uint32_t ua = lds32(sw64(a + 128 * (i & 1)) + 1024 * (i >> 1)), uc = lds32(sw64(a + 4 + 128 * (i & 1)) + 1024 * (i >> 1));
          fx[2 * i] = bf_lo(ua) + bf_hi(ua); fx[2 * i + 1] = bf_hi(ua) + bf_lo(uc);
        }
        const uint32_t y2 = sw128(cw + C_Y2 + 256 * warp + 16 * (lane & 15));
        WG_WAIT(0);
        PRC(5);
#pragma unroll
        for (int i = 0; i < 8; i++) fx[i] = fmaf(f1024, fx[i], a2[4 + i]);
        stsm4(y2 + (lane >> 4) * 1024, pack_bf16(a2[0], a2[1]), pack_bf16(a2[2], a2[3]), pack_bf16(fx[0], fx[1]), pack_bf16(fx[2], fx[3]));
        asm volatile("stmatrix.sync.aligned.m8n8.x2.shared.b16 [%0], {%1,%2};" ::"r"(y2 + 2048), "r"(pack_bf16(fx[4], fx[5])), "r"(pack_bf16(fx[6], fx[7])) : "memory");
      }
      fence_async_smem();
      if (tid == 0) asm volatile("cp.async.bulk.wait_group 0;" ::: "memory");
      bar_sync(nb, 128);
      PRC(6);
      if (lane == 0 && warp) {
        tma3d_red(&M.Yr, cw + C_Y1 + (warp == 3 ? 11264 : warp * 4096), warp == 3 ? 16 : warp * 4, chan);
        BULK_COMMIT();
      }
      PROFC(tid == 0, 32 + wg * 8 + nch);
    }
  }
  int tid = threadIdx.x & 127;
  OPAQUE(tid);
  if ((tid & 31) == 0) asm volatile("cp.async.bulk.wait_group 0;" ::: "memory");
  bar_sync(nb, 128);
  if (tid == 0) { asm volatile("red.relaxed.gpu.global.add.u32 [%0], 1;" ::"l"(P.S->ycnt + prev * 32) : "memory"); PROF(24 + wg); }
}

__device__ __forceinline__ int y_atom(int mi, int t) { const int k = mi >> 4; return k < 2 ? 5 + k : !t ? k - 2 : k == 2 ? 4 : k + 4; }
__device__ __forceinline__ void helper_role(uint32_t sb, const Tile T, int mi, unsigned epoch0, uint32_t ld0, const Params& P, const Maps& M) {
  const uint32_t bars = sb + BARS;
  if (mi < 32) ln_compute<10>(sb, sb + MCW + C_Y1, 96 + mi, P);
  else mbar_wait(bars + 8 * B_LI, 0);
  colsum(sb, T, mi, epoch0 + 1, P);
  kgen_stream<true>(sb, sb + MCW, bars + 8 * B_CV, 3, 0, 1, bars + 8 * (B_CV + 3), ld0, 0);
  mbar_wait(bars + 8 * B_TAB, 0);
  conv_stream<true>(sb, sb + MCW, bars + 8 * B_CV, 3, NPC + mi, 0, 0, 0x21, 0, P, M);
  int tid = threadIdx.x & 127;
  OPAQUE(tid);
  const int warp = tid >> 5, lane = tid & 31;
#pragma unroll 1
  for (int t = 0; t < (mi < 32 ? 1 : 2); t++) {
    const uint32_t yt = sb + ZONE + 16384 + t * ZSZ, st = sb + MCW + 1024 + t * 16384 + warp * 4096;
    uint32_t bb[8];
#pragma unroll
    for (int j = 0; j < 8; j++) bb[j] = lds32(sb + MISC + 128 + t * 128 + (lane & 3) * 4 + j * 16);
    mbar_wait(bars + 8 * (t ? B_YT2 : B_YT), 0);
    PROFC(tid == 0, 121 + 3 * t);
#pragma unroll 1
    for (int h = 0; h < 2; h++) {
      const uint32_t yrow = yt + (warp >> 1) * 8192 + ((lane & 7) + (lane >> 4) * 8) * 128 + ((((warp & 1) * 4 + h * 2 + ((lane >> 3) & 1)) ^ (lane & 7)) << 4);
      const uint32_t row = st + h * 2048 + (lane & 15) * 128;
#pragma unroll
      for (int jj = 0; jj < 4; jj++) {
        uint32_t ry[4];
        ldsm4t(ry, yrow + jj * 2048);
        stsm4(row + (((2 * jj + (lane >> 4)) ^ (lane & 7)) << 4), hadd2(ry[0], bb[2 * jj]), hadd2(ry[1], bb[2 * jj]), hadd2(ry[2], bb[2 * jj + 1]), hadd2(ry[3], bb[2 * jj + 1]));
      }
    }
    fence_async_smem();
    __syncwarp();
    if (lane == 0) {
      const int atom = y_atom(mi, t), r = (mi & 15) * 128 + warp * 32;
      tma2d_red(&M.O, st, atom * 64, r);
      tma2d_red(&M.O, st + 2048, atom * 64, r + 16);
      BULK_COMMIT();
    }
    PROFC(tid == 0, 122 + 3 * t);
  }
  if (lane == 0) asm volatile("cp.async.bulk.wait_group.read 0;" ::: "memory");
  if (tid == 0) { PROF(19); }
}

__global__ void __cluster_dims__(2, 1, 1) __launch_bounds__(512, 1)
fused_kernel(const __grid_constant__ Params P, const __grid_constant__ Maps M) {
  extern __shared__ __align__(1024) unsigned char smem[];
  const uint32_t sb = smem_u32(smem), bars = sb + BARS;
  const int wg = __shfl_sync(0xffffffffu, threadIdx.x >> 7, 0);
  const int rank = blockIdx.x & 1, cl = blockIdx.x >> 1;
  int gpc, slot;
  if (cl < 4) { gpc = 0; slot = cl; }
  else if (cl < 36) { gpc = (cl - 4) & 7; slot = ((cl - 4) >> 3) + (gpc == 0 ? 4 : 0); }
  else if (cl < 64) { gpc = 1 + (cl - 36) % 7; slot = 4 + (cl - 36) / 7; }
  else { gpc = 8; slot = cl - 58; }
  PROFC(threadIdx.x == 0, 0);
  const bool conv = slot >= 6;
  const int c = (gpc * 2 + slot - 6) * 2 + rank, nconv = gridDim.x - NMLP;
  const bool half = 13 * nconv >= 2 * NPC;
  const int p6 = 6 * nconv + (half ? c >> 1 : c), np = p6 < NPC ? 7 : 6;
  const int sp = wg == 3 ? 2 : wg == 1 ? 3 : wg >> 1;
  const int mp = gpc * 6 + slot, mi = mp * 2 + rank;
  const Tile T = {mp & 15, mp >> 4, rank};
  const int atom0 = T.th * 9 + rank * 5, col4 = T.th * 576 + 256 + rank * 32;
  if (!conv && wg == 2) {
    asm volatile("setmaxnreg.dec.sync.aligned.u32 24;");
    if ((threadIdx.x & 31) == 0) {
      const int w = threadIdx.x >> 5;
      if (w < 11) {
      const uint32_t fb = bars + 8 * (B_FULL + w - 8);
      mbar_init(fb, 1); fence_async_smem();
      mbar_expect(fb, SLOT);
      tma3d(sb + (w - 8) * SLOT, &M.W1, (w - 8) * 32, atom0, fb);
      tma2d(sb + (w - 8) * SLOT + 16384, &M.W1h, col4, (w - 8) * 32, fb);
    } else if (w == 11) {
      mbar_init(bars + 8 * B_XF, 1); fence_async_smem();
      mbar_expect(bars + 8 * B_XF, 8192);
      tma2d(sb + XR0, &M.X, 0, T.mt * 128, bars + 8 * B_XF);
      }
    }
    bar_sync(0, 512);
    PROFC(threadIdx.x == 288, 13);
    if (threadIdx.x == 256) {
      int slot2 = 3, ph = 1;
#pragma unroll 1
      for (int n = 3; n < 45; n++) {
        const uint32_t fb = bars + 8 * (B_FULL + slot2);
        if (n >= NSLOT) mbar_wait(bars + 8 * (B_EMPTY + slot2), ph);
        if (n < 20) {
          mbar_expect(fb, SLOT);
          tma3d(sb + slot2 * SLOT, &M.W1, n * 32, atom0, fb);
          tma2d(sb + slot2 * SLOT + 16384, &M.W1h, col4, n * 32, fb);
          if (n == 10) prefetch_l2((const char*)P.w2 + mi * 23040, 23040);
        } else {
          const int a = (n - 20) / 5, u = (n - 20) - 5 * a;
          mbar_expect(fb, u == 2 ? 8192 : 16384);
          tma2d(sb + slot2 * SLOT, u == 2 ? &M.W2 : &M.W22, (rank * 5 + (2 * T.th + a) % 5) * 64, (T.th * 9 + (((rank ? 0x20475 : 0x75420) >> (4 * u)) & 15)) * 64, fb);
        }
        if (++slot2 == NSLOT) { slot2 = 0; ph ^= 1; }
      }
    } else if (threadIdx.x == 288) {
#pragma unroll 1
      for (int n = 1; n < 20; n++) {
        const int k = n >> 1, w = n & 1, xs = k % 3;
        if (k >= 3) mbar_wait(bars + 8 * (B_XE + w * 3 + xs), (k / 3 - 1) & 1);
        mbar_expect(bars + 8 * (B_XF + w * 3 + xs), 8192);
        tma2d(sb + (w ? XR1 : XR0) + xs * 8192, &M.X, k * 64, T.mt * 128 + w * 64, bars + 8 * (B_XF + w * 3 + xs));
      }
    } else if (threadIdx.x == 320) {
      mbar_wait(bars + 8 * B_LI, 0);
      load_par(sb + MCW + C_U, bars + 8 * (B_CV + 2), NPC + mi, P);
      mbar_wait(bars + 8 * B_LN, 0);
      asm volatile("red.release.gpu.global.add.u32 [%0], 1;" ::"l"(&P.S->cnt1) : "memory");
      PROF(16);
      store_x(sb + LNS, mi, M);
      if (mi < 32) store_x(sb + MCW + C_Y1, 96 + mi, M);
      BULK_COMMIT();
      if (mi >= 32) {
        mbar_arrive(bars + 8 * (B_CV + 3));
        mbar_wait(bars + 8 * B_CS, 0);
        asm volatile("red.release.gpu.global.add.u32 [%0], 1;" ::"l"(&P.S->cnt2) : "memory");
      }
      asm volatile("cp.async.bulk.wait_group.read 0;" ::: "memory");
      if (mi < 32) mbar_arrive(bars + 8 * (B_CV + 3));
      mbar_arrive(bars + 8 * B_TAB);
      asm volatile("cp.async.bulk.wait_group 0;" ::: "memory");
      publish(&P.S->cnt3, 1);
    } else if (threadIdx.x >= 352) {
      const int lane = threadIdx.x & 31;
      unsigned epoch;
      asm volatile("ld.global.u32 %0, [%1];" : "=r"(epoch) : "l"(P.S->epoch + blockIdx.x * 4 + 2));
      const unsigned f = T.th * 576 + T.rank * 320 + lane * 4, f2 = T.th * 576 + T.rank * 32 + 256 + (lane & 7) * 4;
      const uint32_t t0 = sb + TCS + lane * 32, t2 = sb + TCS + 2048 + (lane & 7) * 32;
      {
        const uint2 b0 = __ldg((const uint2*)(P.b1 + f)), b1 = __ldg((const uint2*)(P.b1 + f + 128)), b2 = __ldg((const uint2*)(P.b1 + f2));
        auto put = [&](uint32_t a, uint2 b) {
          sts64(a + 8, __float_as_uint(0.5f * bf_lo(b.x)), __float_as_uint(0.5f * bf_hi(b.x)));
          sts64(a + 24, __float_as_uint(0.5f * bf_lo(b.y)), __float_as_uint(0.5f * bf_hi(b.y)));
        };
        put(t0, b0); put(t0 + 1024, b1); put(t2, b2);
      }
      epoch++;
      __syncwarp();
      if (lane == 0) {
        P.S->epoch[blockIdx.x * 4 + 2] = epoch;
        poll_ge(&P.S->cnt1, epoch * NMLP);
      }
      __syncwarp();
      {
        const uint4* sp4 = (const uint4*)(P.S->stats + T.mt * 128) + lane;
        const uint4 s0 = __ldcg(sp4), s1 = __ldcg(sp4 + 32);
        sts128(sb + STATS + lane * 16, s0.x, s0.y, s0.z, s0.w);
        sts128(sb + STATS + lane * 16 + 512, s1.x, s1.y, s1.z, s1.w);
      }
#pragma unroll 1
      for (int t = 0; t < 2; t++) sts32(sb + MISC + 128 + t * 128 + lane * 4, __ldg((const uint32_t*)P.b2 + y_atom(mi, t) * 32 + lane));
      if (lane == 0) poll_ge(&P.S->cnt2, epoch * 64);
      PROFC(lane == 0, 18);
      __syncwarp();
      const float* cs = P.S->csp[epoch & 1];
      const uint4 c0 = __ldcg((const uint4*)(cs + f)), c1 = __ldcg((const uint4*)(cs + f + 128)), c2 = __ldcg((const uint4*)(cs + f2));
      sts64(t0, c0.x, c0.y); sts64(t0 + 16, c0.z, c0.w);
      sts64(t0 + 1024, c1.x, c1.y); sts64(t0 + 1040, c1.z, c1.w);
      sts64(t2, c2.x, c2.y); sts64(t2 + 16, c2.z, c2.w);
      mbar_arrive(bars + 8 * B_TAB);
      PROFC(lane == 0, 17);
      if (lane == 0) {
        poll_ge(&P.S->cnt3, epoch * NMLP);
        mbar_arrive(bars + 8 * B_OUT);
        mbar_wait(bars + 8 * B_HFREE, 0);
#pragma unroll 1
        for (int t = 0; t < (mi < 32 ? 1 : 2); t++) {
          const int atom = y_atom(mi, t);
          const uint32_t yb = bars + 8 * (t ? B_YT2 : B_YT), yt = sb + ZONE + 16384 + t * ZSZ;
          mbar_expect(yb, 16384);
          poll_ge(P.S->ycnt + atom * 32, epoch * 64);
          PROF(120 + 3 * t);
          asm volatile("fence.proxy.async.global;" ::: "memory");
          tma2d(yt, &M.Y, (mi & 15) * 128, atom * 64, yb);
          tma2d(yt + 8192, &M.Y, (mi & 15) * 128 + 64, atom * 64, yb);
        }
      }
    }
    return;
  }
  if ((threadIdx.x & 31) == 0) {
    const int w = threadIdx.x >> 5;
    if (conv) {
      mbar_init(bars + 8 * w, 1);
      if (w < 3) mbar_init(bars + 8 * (B_SP + w), 128);
      fence_async_smem();
      if ((w & 2) && (!(w & 1) || sp < np - 4)) load_par(sb + wg * CW + C_U + (w & 1) * 5120, bars + 8 * w, (w & 1) && sp == 2 ? p6 : ((w & 1) ? 4 + sp : wg) * nconv + c, P);
    } else if (w == 4) {
      mbar_init(bars + 8 * B_LI, 1); fence_async_smem();
      mbar_expect(bars + 8 * B_LI, SLOT);
      tma3d(sb + LNS, &M.Xl, mi * 16, 0, bars + 8 * B_LI);
      if (mi < 32) {
        mbar_init(bars + 8 * B_LI2, 1); fence_async_smem();
        mbar_expect(bars + 8 * B_LI2, SLOT);
        tma3d(sb + MCW + C_Y1, &M.Xl, (96 + mi) * 16, 0, bars + 8 * B_LI2);
      }
      mbar_init(bars + 8 * B_LN, mi < 32 ? 12 : 8);
    } else {
#pragma unroll 1
      for (int i = 3 + w - (w > 4) - 4 * (w > 11); i < NBAR; i += 11) {
        if (i == B_XF || i == B_LI || i == B_LN) continue;
        mbar_init(bars + 8 * i, i == B_CS ? 4 : i < B_EMPTY ? 1 : i < B_LN ? 2 : i == B_TAB ? 33 : i >= B_OUT ? 1 : 8);
        if (i == B_HIN || i == B_HIN + 1) mbar_expect(bars + 8 * i, 36864);
      }
      asm volatile("fence.mbarrier_init.release.cluster;" ::: "memory");
      fence_async_smem();
    }
  }
  bar_sync(0, 512);
  PROFC(threadIdx.x == 128, 1);
  if (conv) {
    const uint32_t ld0 = ld_dt(P, wg * nconv + c), ld1 = ld_dt(P, sp < 2 ? (4 + sp) * nconv + c : p6);
    unsigned target;
    asm volatile("ld.global.u32 %0, [%1];" : "=r"(target) : "l"(P.S->epoch + blockIdx.x * 4 + wg));
    kgen_stream<false>(sb, sb + wg * CW, bars + 32 * wg, wg, sp, sp < np - 4 ? 2 : 1, 0, ld0, ld1);
    if ((threadIdx.x & 127) == 32) P.S->epoch[blockIdx.x * 4 + wg] = target += NMLP;
    conv_stream<false>(sb, sb + wg * CW, bars + 32 * wg, wg, wg * nconv + c, nconv, p6,
                np == 6 ? (wg == 0 ? 0x521 : wg == 2 ? 0x621 : wg == 1 ? 0x321 : 0x421) : half ? (wg == 0 ? 0x521 : wg == 2 ? 0x621 : wg == 3 ? 0x721 + (c & 1) * 0x100 : 0x4321) : (wg == 0 ? 0x721 : wg == 2 ? 0x821 : wg == 3 ? 0x521 : 0x63421), target, P, M);
    PROFDUMP();
    return;
  }
  if (wg < 2) {
    ln_compute<5>(sb, sb + LNS, mi, P);
    asm volatile("setmaxnreg.inc.sync.aligned.u32 208;");
    mlp_role(sb, wg, T, P, M);
    PROFDUMP();
    return;
  }
  asm volatile("setmaxnreg.dec.sync.aligned.u32 72;");
  const uint32_t ld0 = ld_dt(P, NPC + mi);
  unsigned target;
  asm volatile("ld.global.u32 %0, [%1];" : "=r"(target) : "l"(P.S->epoch + blockIdx.x * 4 + 3));
  helper_role(sb, T, mi, target, ld0, P, M);
  PROFDUMP();
}

typedef CUresult (*EncodeFn)(CUtensorMap*, CUtensorMapDataType, cuuint32_t, void*, const cuuint64_t*, const cuuint64_t*, const cuuint32_t*,
                             const cuuint32_t*, CUtensorMapInterleave, CUtensorMapSwizzle, CUtensorMapL2promotion, CUtensorMapFloatOOBfill);

void make_map(EncodeFn enc, CUtensorMap* tm, const void* base, int nd, const cuuint64_t* dims, const cuuint64_t* strides, const cuuint32_t* box, CUtensorMapSwizzle sw) {
  cuuint32_t es[3] = {1, 1, 1};
  enc(tm, CU_TENSOR_MAP_DATA_TYPE_BFLOAT16, nd, const_cast<void*>(base), dims, strides, box, es, CU_TENSOR_MAP_INTERLEAVE_NONE,
      sw, CU_TENSOR_MAP_L2_PROMOTION_NONE, CU_TENSOR_MAP_FLOAT_OOB_FILL_NONE);
}
void make_map2(EncodeFn enc, CUtensorMap* tm, const void* base, int rows, int cols, int box_rows, int box_cols = 64, CUtensorMapSwizzle sw = CU_TENSOR_MAP_SWIZZLE_128B) {
  cuuint64_t dims[2] = {(cuuint64_t)cols, (cuuint64_t)rows}, strides[1] = {(cuuint64_t)cols * 2};
  cuuint32_t box[2] = {(cuuint32_t)box_cols, (cuuint32_t)box_rows};
  make_map(enc, tm, base, 2, dims, strides, box, sw);
}

}

extern "C" void kernel_launch(void* const* d_in, const int* in_sizes, int n_in, void* d_out, int out_size) {
  static EncodeFn enc = nullptr;
  static Scratch* S = nullptr;
  static int grid = 128;
  if (!enc) {
    void* fn = nullptr;
    cudaDriverEntryPointQueryResult qr;
    cudaGetDriverEntryPoint("cuTensorMapEncodeTiled", &fn, cudaEnableDefault, &qr);
    enc = (EncodeFn)fn;
    cudaGetSymbolAddress((void**)&S, g_s);
    cudaFuncSetAttribute(fused_kernel, cudaFuncAttributeMaxDynamicSharedMemorySize, SMEM_BYTES);
    cudaLaunchConfig_t cfg = {};
    cudaLaunchAttribute at;
    at.id = cudaLaunchAttributeClusterDimension; at.val.clusterDim.x = 2; at.val.clusterDim.y = 1; at.val.clusterDim.z = 1;
    cfg.gridDim = dim3(132); cfg.blockDim = dim3(512); cfg.dynamicSmemBytes = SMEM_BYTES; cfg.attrs = &at; cfg.numAttrs = 1;
    int ncl = 0;
    if (cudaOccupancyMaxActiveClusters(&ncl, fused_kernel, &cfg) == cudaSuccess && ncl >= 66) grid = 132;
    cudaGetLastError();
  }
  Params P;
  P.x = (const __nv_bfloat16*)d_in[0];
  P.Are = (const __nv_bfloat16*)d_in[1]; P.Aim = (const __nv_bfloat16*)d_in[2];
  P.Bre = (const __nv_bfloat16*)d_in[3]; P.Bim = (const __nv_bfloat16*)d_in[4];
  P.Cre = (const __nv_bfloat16*)d_in[5]; P.Cim = (const __nv_bfloat16*)d_in[6];
  P.logdt = (const __nv_bfloat16*)d_in[7]; P.dskip = (const __nv_bfloat16*)d_in[8];
  P.w1 = (const __nv_bfloat16*)d_in[10]; P.b1 = (const __nv_bfloat16*)d_in[11];
  P.w2 = (const __nv_bfloat16*)d_in[12]; P.b2 = (const __nv_bfloat16*)d_in[13];
  P.S = S;
  const void *yT = S->yT, *xnT = S->xnT;
  Maps M;
  make_map2(enc, &M.X, P.x, SEQ, DM, 64);
  {
    cuuint64_t dims[3] = {64, DM, FF / 64}, strides[2] = {FF * 2, 128};
    cuuint32_t box[3] = {64, 32, 4};
    make_map(enc, &M.W1, P.w1, 3, dims, strides, box, CU_TENSOR_MAP_SWIZZLE_128B);
  }
  make_map2(enc, &M.W1h, P.w1, DM, FF, 32);
  make_map2(enc, &M.W2, P.w2, FF, DM, 64);
  make_map2(enc, &M.W22, P.w2, FF, DM, 128);
  make_map2(enc, &M.Y, yT, DM, SEQ, 64);
  make_map2(enc, &M.O, d_out, SEQ, DM, 16);
  {
    cuuint64_t dims[3] = {64, SEQ, 10}, strides[2] = {DM * 2, 128};
    cuuint32_t box[3] = {64, 16, 10};
    make_map(enc, &M.Xl, P.x, 3, dims, strides, box, CU_TENSOR_MAP_SWIZZLE_128B);
    make_map(enc, &M.Ol, d_out, 3, dims, strides, box, CU_TENSOR_MAP_SWIZZLE_128B);
  }
  make_map2(enc, &M.U, xnT, DM * 64, 32, 64, 32, CU_TENSOR_MAP_SWIZZLE_64B);
  {
    cuuint64_t dims[3] = {64, 32, DM}, strides[2] = {128, SEQ * 2};
    cuuint32_t box[3] = {64, 32, 1};
    make_map(enc, &M.Yr, yT, 3, dims, strides, box, CU_TENSOR_MAP_SWIZZLE_128B);
  }
  fused_kernel<<<grid, 512, SMEM_BYTES>>>(P, M);
}
```
